```python
import torch

def _softmax(x, axis=-1):
    return torch.softmax(x, dim=axis)
def _gelu(x):
    return torch.nn.functional.gelu(x, approximate="tanh")
def _silu(x):
    return torch.nn.functional.silu(x)
def _sigmoid(x):
    return torch.sigmoid(x)
def _layernorm(x, axis=-1, eps=1e-5):
    m = x.mean(dim=axis, keepdim=True)
    v = x.var(dim=axis, keepdim=True, unbiased=False)
    return (x - m) / torch.sqrt(v + eps)
def _scatter_add(tgt, idx, src, axis=0):
    return tgt.clone().index_add_(axis, idx, src)
def _segment_sum(src, seg, n):
    out = torch.zeros((n,) + src.shape[1:], dtype=src.dtype)
    return out.index_add_(0, seg, src)
def _pad(x, pw):
    flat = tuple(v for pair in reversed(pw) for v in pair)
    return torch.nn.functional.pad(x, flat)

kernel_name = 'interleave_layers__sliding_block_cached__gqa_block_cached__decode'

def setup_inputs():

    _w = (lambda a: (lambda t: t.to(torch.bfloat16) if t.is_floating_point() else t)(torch.as_tensor(a)))
    def _A_setup():
        B, Sq, D = 2, 1, 640
        Hq, Hkv, Sk, Dh = 32, 32, 4096, 192
        assert Hq % Hkv == 0, (Hq, Hkv)
        return {
            "x": _w((lambda *s: torch.randn(*s, dtype=torch.bfloat16) * 0.1)(B, Sq, D)),
            "k_cache": _w((lambda *s: torch.randn(*s, dtype=torch.bfloat16) * 0.8)(B, Hkv, Sk, Dh)),
            "v_cache": _w((lambda *s: torch.randn(*s, dtype=torch.bfloat16) * 3.2)(B, Hkv, Sk, Dh)),
            "wq": _w((lambda *s: torch.randn(*s, dtype=torch.bfloat16) * 0.8)(D, Hq * Dh) * (D ** -0.5)),
            "wo": _w((lambda *s: torch.randn(*s, dtype=torch.bfloat16) * 3.2)(Hq * Dh, D) * ((Hq * Dh) ** -0.5)),
        }
    _A_in = _A_setup()

    def _B_setup():
        B, Sq, D = 2, 1, 640
        Hq, Hkv, Sk, Dh = 32, 32, 4096, 192
        assert Hq % Hkv == 0, (Hq, Hkv)
        return {
            "x": _w((lambda *s: torch.randn(*s, dtype=torch.bfloat16) * 0.1)(B, Sq, D)),
            "k_cache": _w((lambda *s: torch.randn(*s, dtype=torch.bfloat16) * 1.6)(B, Hkv, Sk, Dh)),
            "v_cache": _w((lambda *s: torch.randn(*s, dtype=torch.bfloat16) * 1.6)(B, Hkv, Sk, Dh)),
            "wq": _w((lambda *s: torch.randn(*s, dtype=torch.bfloat16) * 1.6)(D, Hq * Dh) * (D ** -0.5)),
            "wo": _w((lambda *s: torch.randn(*s, dtype=torch.bfloat16) * 1.6)(Hq * Dh, D) * ((Hq * Dh) ** -0.5)),
        }
    _B_in = _B_setup()

    return {
        "A_x": _A_in["x"],
        "A_k_cache": _A_in["k_cache"],
        "A_v_cache": _A_in["v_cache"],
        "A_wq": _A_in["wq"],
        "A_wo": _A_in["wo"],
        "B_x": _B_in["x"],
        "B_k_cache": _B_in["k_cache"],
        "B_v_cache": _B_in["v_cache"],
        "B_wq": _B_in["wq"],
        "B_wo": _B_in["wo"],
    }

def reference(A_x, A_k_cache, A_v_cache, A_wq, A_wo, B_x, B_k_cache, B_v_cache, B_wq, B_wo):
    def _A_ref(x, k_cache, v_cache, wq, wo):
        B, Sq, D = x.shape
        Hq, Dh = 32, 192
        Hkv, Sk = k_cache.shape[1], k_cache.shape[2]
        W = min(4096, max(256, Sk // 4))
        rep = Hq // Hkv
        q = (lambda x, *d: x.permute(*d))((x @ wq).reshape(B, Sq, Hq, Dh), 0, 2, 1, 3)
        k = (lambda x, n, axis: torch.repeat_interleave(x, n, dim=axis))(k_cache[:, :, Sk - W:, :], rep, axis=1)
        v = (lambda x, n, axis: torch.repeat_interleave(x, n, dim=axis))(v_cache[:, :, Sk - W:, :], rep, axis=1)
        scores = torch.einsum("bhqd,bhkd->bhqk", q, k) * (Dh ** -0.5)
        p = _softmax(scores, axis=-1)
        o = torch.einsum("bhqk,bhkd->bhqd", p, v)
        return (lambda x, *d: x.permute(*d))(o, 0, 2, 1, 3).reshape(B, Sq, Hq * Dh) @ wo

    def _B_ref(x, k_cache, v_cache, wq, wo):
        B, Sq, D = x.shape
        Hq, Dh = 32, 192
        Hkv = k_cache.shape[1]
        rep = Hq // Hkv
        q = (lambda x, *d: x.permute(*d))((x @ wq).reshape(B, Sq, Hq, Dh), 0, 2, 1, 3)
        k = (lambda x, n, axis: torch.repeat_interleave(x, n, dim=axis))(k_cache, rep, axis=1)
        v = (lambda x, n, axis: torch.repeat_interleave(x, n, dim=axis))(v_cache, rep, axis=1)
        scores = torch.einsum("bhqd,bhkd->bhqk", q, k) * (Dh ** -0.5)
        p = _softmax(scores, axis=-1)
        o = torch.einsum("bhqk,bhkd->bhqd", p, v)
        return (lambda x, *d: x.permute(*d))(o, 0, 2, 1, 3).reshape(B, Sq, Hq * Dh) @ wo

    x = A_x
    x = x + _A_ref(_layernorm(x, axis=-1), A_k_cache, A_v_cache, A_wq, A_wo)
    x = x + _B_ref(_layernorm(x, axis=-1), B_k_cache, B_v_cache, B_wq, B_wo)
    x = x + _A_ref(_layernorm(x, axis=-1), A_k_cache, A_v_cache, A_wq, A_wo)
    x = x + _B_ref(_layernorm(x, axis=-1), B_k_cache, B_v_cache, B_wq, B_wo)
    return x
```

```cpp
#include <cuda_runtime.h>
#include <cuda_bf16.h>
#include <cuda.h>
#include <stdint.h>

#define SCHED_NPRO 5
#define SCHED_NOPS 92
#define SCHED_NLD 169
#define SCHED_NEV 24
#define SCHED_OPS \
  0x04010409u, 0x1811040du, 0x00000062u, 0x00800082u, 0x00609078u, 0x006918a0u, 0x0077a0e0u, 0x057a4600u, \
  0x00804e5cu, 0x143a5aa1u, 0x0083e2e4u, 0x00830804u, 0x04209479u, 0x188390c4u, 0x0183a0e8u, 0x0003ca00u, \
  0x084bd2c5u, 0x00060300u, 0x00079840u, 0x00079c80u, 0x0007c100u, 0x0007da40u, 0x0007de80u, 0x00078300u, \
  0x00079840u, 0x00039c80u, 0x1840947du, 0x00804100u, 0x0007da40u, 0x0007de80u, 0x0007d660u, 0x04826220u, \
  0x0005180cu, 0x00055a04u, 0x14581811u, 0x000782c4u, 0x0082c0c4u, 0x043302c9u, 0x0083da04u, 0x34000018u, \
  0x00051804u, 0x00055a04u, 0x04381801u, 0x000782c4u, 0x0067c0c4u, 0x00ea82c4u, 0x143b40d9u, 0x00f39804u, \
  0x01005e88u, 0x007d5a04u, 0x00001240u, 0x00005660u, 0x000380e4u, 0x00006220u, 0x010008c4u, 0x00078e84u, \
  0x080004a4u, 0x0083cd00u, 0x00050f00u, 0x183c4d15u, 0x0007a060u, 0x0007e260u, 0x0083a060u, 0x0831e26du, \
  0x0083cd00u, 0x00050f1cu, 0x00054d04u, 0x00050f04u, 0x18064d04u, 0x00838f00u, 0x00054d00u, 0x08340f05u, \
  0x0007e260u, 0x0007a060u, 0x0082e260u, 0x1839a07du, 0x04838f00u, 0x00054d0cu, 0x000500e4u, 0x00050f04u, \
  0x008108c4u, 0x000104a4u, 0x141442f1u, 0x00015a64u, 0x20800004u, 0x00004a84u, 0x000146a4u, 0x00011864u, \
  0x00078884u, 0x000604a4u, 0x0800da64u, 0x180442f7u
#define SCHED_LDS \
  0x00000204u, 0x0000060cu, 0x00000b14u, 0x00000018u, 0x00000021u, 0x00001028u, 0x00001031u, 0x00002038u, \
  0x00002041u, 0x00003000u, 0x00003009u, 0x00200010u, 0x00200019u, 0x00000a25u, 0x0000022du, 0x00000635u, \
  0x00201038u, 0x00201041u, 0x00202000u, 0x00000b0eu, 0x00202011u, 0x0000021eu, 0x0000062eu, 0x00203030u, \
  0x00203021u, 0x0000003au, 0x00000043u, 0x00001002u, 0x00001013u, 0x00000235u, 0x00000625u, 0x00000a3du, \
  0x00002042u, 0x00002003u, 0x00003012u, 0x00003033u, 0x00004022u, 0x0000403bu, 0x00005042u, 0x00005003u, \
  0x00006012u, 0x00006033u, 0x00007022u, 0x0000703bu, 0x00008042u, 0x00008003u, 0x00009012u, 0x00009033u, \
  0x0000a022u, 0x0000a03bu, 0x0000b042u, 0x0000b003u, 0x0000f012u, 0x0000f0b3u, 0x0000c022u, 0x0000c03bu, \
  0x0000d01au, 0x0000d02bu, 0x0000e00au, 0x0000e043u, 0x00200002u, 0x00200033u, 0x00201002u, 0x00201033u, \
  0x00000207u, 0x00000637u, 0x00000a07u, 0x00202032u, 0x00202003u, 0x00203032u, 0x00203003u, 0x00000034u, \
  0x00000604u, 0x00000b34u, 0x00204002u, 0x00204033u, 0x00205002u, 0x00205033u, 0x00206002u, 0x00206033u, \
  0x00000205u, 0x00000635u, 0x00000a05u, 0x00207032u, 0x00207003u, 0x00208032u, 0x00208003u, 0x00209032u, \
  0x00209003u, 0x00000236u, 0x00000606u, 0x00000b36u, 0x0020a002u, 0x0020a033u, 0x0020b002u, 0x0020b033u, \
  0x0000f0a3u, 0x0020c03au, 0x0020c003u, 0x0020d032u, 0x0020d013u, 0x0020f022u, 0x0020f09bu, 0x0020e02au, \
  0x0020e00bu, 0x00000042u, 0x0000001bu, 0x00001042u, 0x0000101bu, 0x00000247u, 0x0000061fu, 0x00000a47u, \
  0x0000201au, 0x00002043u, 0x0000301au, 0x00003043u, 0x0000401au, 0x00004043u, 0x0000001cu, 0x00000444u, \
  0x0000091cu, 0x00005042u, 0x0000501bu, 0x00200040u, 0x00200019u, 0x00201040u, 0x00201019u, 0x00202040u, \
  0x00202019u, 0x00203040u, 0x00203019u, 0x00006042u, 0x0000601bu, 0x00007042u, 0x0000701bu, 0x00000045u, \
  0x0000041du, 0x00000845u, 0x0000801au, 0x00008043u, 0x0000901au, 0x00009043u, 0x0000a01au, 0x0000a043u, \
  0x0000001eu, 0x00000446u, 0x0000091eu, 0x0000b042u, 0x0000b01bu, 0x00200042u, 0x0020001bu, 0x00201042u, \
  0x0020101bu, 0x0000003fu, 0x00000407u, 0x00000847u, 0x0020201au, 0x00202033u, 0x0020f093u, 0x0020302au, \
  0x0020300bu, 0x0020401au, 0x00204033u, 0x00205022u, 0x00205013u, 0x0020602au, 0x0020600bu, 0x0020701au, \
  0x00207033u
#define SCHED_EVS \
  0x00006c00u, 0x00006c24u, 0x00006c01u, 0x00006c02u, 0x00006c28u, 0x00006c05u, 0x00006c06u, 0x00006c2cu, \
  0x00006c09u, 0x00006c0au, 0x00006c30u, 0x00006c11u, 0x00006c12u, 0x00006c38u, 0x00006c0du, 0x00006c0eu, \
  0x00006c34u, 0x00006c15u, 0x00006c16u, 0x00006c3cu, 0x00006c19u, 0x00006c1au, 0x00006c3du, 0x00006c1eu

namespace {

constexpr int kGrid = 128;
constexpr int kThreads = 384;
constexpr int kConsumerRegs = 240;
constexpr int kSlots = 9;
constexpr int kSlotBytes = 3072;

constexpr int OFF_FBUF = 8 * kSlots * kSlotBytes;
constexpr int kFRow    = 784;
constexpr int OFF_Q    = OFF_FBUF + 8 * kFRow;
constexpr int OFF_VEC  = OFF_Q + 768;
constexpr int OFF_OPS  = OFF_VEC + 768;
constexpr int OFF_LDS  = OFF_OPS + 128 * 4;
constexpr int OFF_BAR  = OFF_LDS + 256 * 4;
constexpr int OFF_EVS  = OFF_BAR + 76 * 8;
constexpr int OFF_SCR  = OFF_EVS + 96;
constexpr int kSmemBytes = OFF_SCR + 128;
static_assert(kSmemBytes <= 232448, "shared memory budget");
static_assert(SCHED_NOPS < 128 && SCHED_NLD < 256 && SCHED_NEV <= 24, "table size");

constexpr int BAR_READY = OFF_BAR + 72 * 8;
constexpr int BAR_FFULL = BAR_READY + 16;
constexpr int BAR_FEMPTY = BAR_FFULL + 8;

constexpr int kRecWords = 128;
constexpr int kXCopies = 4;
constexpr uint32_t kSpinLimit = 1u << 22;
constexpr uint64_t kKeepPolicy = 0x1000000000000000ull;
constexpr uint64_t kStreamPolicy = 0x12F0000000000000ull;
constexpr uint32_t kL1Warps = 7;
constexpr uint32_t kRecDelayNs = 200, kRecPollNs = 200, kRowDelayNs = 700, kRowPollNs = 300;

struct Params {
    CUtensorMap maps[8];
    const __nv_bfloat16* x;
    __nv_bfloat16* out;
    const char* vb;
};

__device__ const uint32_t g_ops[128] = { SCHED_OPS, 0xffffffffu };
__device__ const uint32_t g_lds[256] = { SCHED_LDS };
__device__ const uint32_t g_evs[SCHED_NEV] = { SCHED_EVS };

struct __align__(128) Scratch {
    uint2 rec[2 * kGrid * kRecWords];
    uint2 row[2 * 4 * kXCopies * 640];
    uint32_t rank[SCHED_NEV * 32];
    uint32_t epoch;
};
__device__ Scratch g_scratch;

__device__ __forceinline__ void mbar_init(uint32_t a, uint32_t c) {
    asm volatile("mbarrier.init.shared::cta.b64 [%0], %1;" :: "r"(a), "r"(c) : "memory");
}
__device__ __forceinline__ void mbar_arrive(uint32_t a) {
    asm volatile("mbarrier.arrive.shared::cta.b64 _, [%0];" :: "r"(a) : "memory");
}
__device__ __forceinline__ void mbar_wait(uint32_t a, uint32_t parity) {
    asm volatile(
        "{\n.reg .pred p;\n.reg .u32 n;\nmov.u32 n, 0;\n"
        "WAIT: mbarrier.try_wait.parity.shared::cta.b64 p, [%0], %1;\n"
        "@p bra DONE;\nadd.u32 n, n, 1;\nsetp.lt.u32 p, n, %2;\n@p bra WAIT;\ntrap;\nDONE:\n}"
        :: "r"(a), "r"(parity), "n"(kSpinLimit) : "memory");
}
__device__ __forceinline__ void lds128(uint32_t* r, uint32_t a) {
    asm volatile("ld.shared.v4.u32 {%0,%1,%2,%3}, [%4];" : "=r"(r[0]), "=r"(r[1]), "=r"(r[2]), "=r"(r[3]) : "r"(a) : "memory");
}
__device__ __forceinline__ uint32_t lds32(uint32_t a) {
    uint32_t v; asm volatile("ld.shared.u32 %0, [%1];" : "=r"(v) : "r"(a) : "memory"); return v;
}
__device__ __forceinline__ uint32_t lds16(uint32_t a) {
    unsigned short v; asm volatile("ld.shared.u16 %0, [%1];" : "=h"(v) : "r"(a) : "memory"); return v;
}
__device__ __forceinline__ float ldsf(uint32_t a) {
    float v; asm volatile("ld.shared.f32 %0, [%1];" : "=f"(v) : "r"(a) : "memory"); return v;
}
__device__ __forceinline__ uint2 lds64(uint32_t a) {
    uint2 v; asm volatile("ld.shared.v2.u32 {%0,%1}, [%2];" : "=r"(v.x), "=r"(v.y) : "r"(a) : "memory"); return v;
}
__device__ __forceinline__ void sts32(uint32_t a, uint32_t v) { asm volatile("st.shared.u32 [%0], %1;" :: "r"(a), "r"(v) : "memory"); }
__device__ __forceinline__ void stsf(uint32_t a, float v) { asm volatile("st.shared.f32 [%0], %1;" :: "r"(a), "f"(v) : "memory"); }
__device__ __forceinline__ void sts16(uint32_t a, uint32_t v) { asm volatile("st.shared.u16 [%0], %1;" :: "r"(a), "h"((unsigned short)v) : "memory"); }
__device__ __forceinline__ void sts128f(uint32_t a, const float* v) {
    asm volatile("st.shared.v4.f32 [%0], {%1,%2,%3,%4};" :: "r"(a), "f"(v[0]), "f"(v[1]), "f"(v[2]), "f"(v[3]) : "memory");
}
__device__ __forceinline__ void mma(float* d, uint32_t a0, uint32_t a1, uint32_t a2, uint32_t a3, uint32_t b0, uint32_t b1) {
    asm volatile("mma.sync.aligned.m16n8k16.row.col.f32.bf16.bf16.f32 {%0,%1,%2,%3}, {%4,%5,%6,%7}, {%8,%9}, {%0,%1,%2,%3};"
        : "+f"(d[0]), "+f"(d[1]), "+f"(d[2]), "+f"(d[3]) : "r"(a0), "r"(a1), "r"(a2), "r"(a3), "r"(b0), "r"(b1));
}
__device__ __forceinline__ float exp_diff(float x, float m) {
    float y; asm("ex2.approx.ftz.f32 %0, %1;" : "=f"(y) : "f"((x - m) * 1.4426950408889634f)); return y;
}
__device__ __forceinline__ uint32_t pack_bf16(float lo, float hi) {
    uint32_t r; asm("cvt.rn.bf16x2.f32 %0, %1, %2;" : "=r"(r) : "f"(hi), "f"(lo)); return r;
}
__device__ __forceinline__ float bf_lo(uint32_t w) { return __uint_as_float(w << 16); }
__device__ __forceinline__ float bf_hi(uint32_t w) { return __uint_as_float(w & 0xffff0000u); }
__device__ __forceinline__ float bf_round(float x) { return bf_lo(pack_bf16(x, 0.f)); }

__device__ __forceinline__ void st_word(uint2* p, uint32_t lo, uint32_t hi) {
    asm volatile("st.relaxed.gpu.global.L1::no_allocate.b64 [%0], %1;" :: "l"(p), "l"(((uint64_t)hi << 32) | lo) : "memory");
}
__device__ __forceinline__ void st_pair(uint2* p, float a, float b, uint32_t tag) {
    const uint32_t ua = __float_as_uint(a), ub = __float_as_uint(b);
    st_word(p, __byte_perm(ua, ub, 0x3217), __byte_perm(ub, tag, 0x5421));
}
__device__ __forceinline__ float pair_a(uint32_t lo) { return __uint_as_float(lo & 0xffffff00u); }
__device__ __forceinline__ float pair_b(uint32_t lo, uint32_t hi) { return __uint_as_float(__byte_perm(lo, hi, 0x0544) & 0xffffff00u); }
__device__ __forceinline__ uint2 ld_word(const uint2* p) {
    uint64_t w;
    asm volatile("ld.relaxed.gpu.global.L1::no_allocate.b64 %0, [%1];" : "=l"(w) : "l"(p) : "memory");
    return make_uint2((uint32_t)w, (uint32_t)(w >> 32));
}
__device__ __forceinline__ unsigned long long row_word(float v) { return ((unsigned long long)__float2ll_rn(v * 16777216.f) << 6) + 1; }
__device__ __forceinline__ void row_add(uint2* p, unsigned long long w, uint32_t go = 1) {
    asm volatile("{\n.reg .pred p;\nsetp.ne.u32 p, %2, 0;\n@p red.relaxed.gpu.global.add.u64 [%0], %1;\n}" :: "l"(p), "l"(w), "r"(go) : "memory");
}
__device__ __forceinline__ float row_value(uint2 w) {
    const long long sum = (long long)(((uint64_t)w.y << 48) | ((uint64_t)w.x << 16)) >> 22;
    const float prev = __uint_as_float((w.y + 0x8000u) & 0xffff0000u);
    return bf_round(prev + bf_round(__ll2float_rn(sum) * (1.f / 16777216.f)));
}
__device__ __forceinline__ uint32_t svc_tid() { uint32_t t; asm volatile("mov.u32 %0, %%tid.x;" : "=r"(t)); return t - 256; }
__device__ __forceinline__ void svc_sync() { asm volatile("bar.sync 1, 128;" ::: "memory"); }

__device__ __forceinline__ uint32_t uniform(uint32_t v) { return __shfl_sync(0xffffffffu, v, 0); }

struct Load { uint32_t dst, bar, bytes; int row, line; const CUtensorMap* map; uint64_t pol; };
__device__ __forceinline__ Load decode(uint32_t e, uint32_t sb, const Params& P, uint32_t warp) {
    Load d;
    const uint32_t s = warp * kSlots + ((e >> 3) & 15u);
    d.dst = sb + s * kSlotBytes;
    d.bar = sb + OFF_BAR + s * 8;
    d.bytes = (e & (warp << 6) & 0x100u) ? 0 : kSlotBytes;
    d.row = (int)((((e >> 16) & 0x7fffu) + warp) * 8);
    d.line = (int)((e >> 9) & 127u);
    d.map = &P.maps[e & 7u];
    d.pol = (int)e < 0 ? kKeepPolicy : kStreamPolicy;
    return d;
}
__device__ __forceinline__ void fire(const Load& d, uint32_t go) {
    asm volatile(
        "{\n.reg .pred p, q;\n"
        "elect.sync _|p, 0xffffffff;\n"
        "setp.ne.and.u32 p, %7, 0, p;\n"
        "@p mbarrier.arrive.expect_tx.shared::cta.b64 _, [%2], %6;\n"
        "setp.ne.and.u32 q, %6, 0, p;\n"
        "@q cp.async.bulk.tensor.3d.shared::cluster.global.tile.mbarrier::complete_tx::bytes.L2::cache_hint"
        " [%0], [%1, {0, %3, %4}], [%2], %5;\n}"
        :: "r"(d.dst), "l"(d.map), "r"(d.bar), "r"(d.row), "r"(d.line), "l"(d.pol), "r"(d.bytes), "r"(go) : "memory");
}
__device__ __forceinline__ void fire_l1(const Load& d, const char* base, uint32_t lane) {
    const uint32_t r = lane >> 2, t = lane & 3;
    const char* src = base + (size_t)(d.row + r) * 384 + t * 16;
    const uint32_t dst = d.dst + r * 128 + ((t ^ r) << 4);
#pragma unroll
    for (int i = 0; i < 6; i++)
        asm volatile("cp.async.ca.shared.global.L2::cache_hint [%0], [%1], 16, %2;"
            :: "r"((dst ^ ((i & 1) * 64u)) + (i >> 1) * 1024), "l"(src + (i >> 1) * 128 + (i & 1) * 64), "l"(d.pol) : "memory");
    asm volatile("cp.async.mbarrier.arrive.shared::cta.b64 [%0];" :: "r"(d.bar) : "memory");
    __syncwarp();
    if (lane == 0) mbar_arrive(d.bar);
}
__device__ __forceinline__ uint32_t expand_entry(uint32_t e, uint32_t h, uint32_t j) {
    const uint32_t mp = e & 7u;
    const uint32_t row8 = mp < 4 ? h * 512 + j * 8 + (mp < 2 ? 384 : 0) : (mp & 1) ? h * 24 : j * 20;
    const uint32_t line = mp < 4 ? 0 : mp == 5 ? 3 * j : mp == 7 ? 3 * ((j + 2) & 3) : 3 * h;
    return (e & 0x1ffu) | (line << 9) | ((row8 + (e >> 10) * 8) << 16) | ((e & 0x200u) << 22);
}
__device__ __forceinline__ uint32_t after(float a, float b, float c, uint32_t zero) {
    uint32_t r;
    asm volatile("{\n.reg .b32 x, y, z;\nmov.b32 x, %1;\nmov.b32 y, %2;\nmov.b32 z, %3;\nlop3.b32 x, x, y, z, 0xfe;\nand.b32 %0, x, %4;\n}"
        : "=r"(r) : "f"(a), "f"(b), "f"(c), "r"(zero));
    return r;
}
__device__ __forceinline__ uint32_t opaque(uint32_t v) { asm volatile("" : "+r"(v)); return v; }
__device__ __forceinline__ int mono(int b) { return b ^ ((b >> 31) & 0x7fffffff); }

__device__ __forceinline__ void qk_regs(const uint32_t* k, float* d1, float* d2, uint32_t qa) {
#pragma unroll
    for (int c = 0; c < 6; c++) {
        uint32_t q[4]; lds128(q, qa + c * 64);
        mma(d1, q[0], q[1], q[2], q[3], k[4 * c], k[4 * c + 1]);
        mma(d2, q[0], q[1], q[2], q[3], k[4 * c + 2], k[4 * c + 3]);
    }
}
__device__ __forceinline__ void k_fetch(uint32_t* k, uint32_t ka) {
#pragma unroll
    for (int c = 0; c < 3; c++) { lds128(k + 8 * c, ka + c * 1024); lds128(k + 8 * c + 4, (ka ^ 64u) + c * 1024); }
}
__device__ __forceinline__ void v_fetch(uint32_t* v, uint32_t va) {
#pragma unroll
    for (int c = 0; c < 3; c++) { lds128(v + 8 * c, va + c * 1024); lds128(v + 8 * c + 4, (va ^ 576u) + c * 1024); }
}
__device__ __forceinline__ void pv_regs(const uint32_t* v, float (*acc)[4], const uint32_t* b) {
#pragma unroll
    for (int c = 0; c < 3; c++) {
        mma(acc[c], v[8 * c], v[8 * c + 1], v[8 * c + 2], v[8 * c + 3], b[0], b[1]);
        mma(acc[c], v[8 * c + 4], v[8 * c + 5], v[8 * c + 6], v[8 * c + 7], b[2], b[3]);
    }
}

__device__ __forceinline__ void make_b(uint32_t* b, uint32_t w, uint32_t pk, uint32_t ch) {
    if ((pk >> 24) != ch) w = 0;
    const uint32_t sel = __funnelshift_l(0x44444410u, 0x44444410u, (pk >> 19) & 0x18u);
    b[0] = __byte_perm(w, 0, sel); b[1] = __byte_perm(w, 0, sel >> 16);
    w >>= 16;
    b[2] = __byte_perm(w, 0, sel); b[3] = __byte_perm(w, 0, sel >> 16);
}

__device__ __forceinline__ void consumer(const Params& P, uint32_t sb, uint32_t warp, uint32_t lane_in) {
    uint32_t rk[4][24], rv[4][24];
#pragma unroll
    for (int r = 0; r < 4; r++)
#pragma unroll
        for (int i = 0; i < 24; i++) { rk[r][i] = 0; rv[r][i] = 0; }
    float acc[3][4];
#pragma unroll
    for (int c = 0; c < 3; c++) { acc[c][0] = acc[c][1] = acc[c][2] = acc[c][3] = 0.f; }
    constexpr int kMinusInf = (int)0x807fffffu;
    int mkv = kMinusInf;
    float l = 0.f;

    uint32_t pk;
    {
        const uint32_t g = lane_in >> 2, t = lane_in & 3;
        const uint32_t keyg = ((g & 6u) + (g >> 2)) ^ ((g & 1u) << 2);
        const uint32_t keyt = 2 * t + (t >> 1);
        pk = (keyg * 128 + ((t ^ keyg) << 4)) | ((keyt * 128 + ((g ^ keyt) << 4)) << 10) | (lane_in << 20);
    }
    const uint32_t wslot = sb + warp * (kSlots * kSlotBytes);
    const uint32_t wbar = sb + OFF_BAR + warp * (kSlots * 8);
    uint32_t lptr = sb + OFF_LDS + SCHED_NPRO * 4;
    uint32_t e = uniform(lds32(lptr));
    Load nx = decode(e, sb, P, warp);
    uint32_t optr = sb + OFF_OPS;
    uint32_t op = uniform(lds32(optr));
    uint32_t ahead = 0, boost = 0;

#define ACC_DEP after(acc[0][0], acc[1][0], acc[2][0], zero)
#define ADVANCE(go) do { lptr += (go) ? 4 : 0; e = uniform(lds32(lptr)); nx = decode(e, sb, P, warp); } while (0)

#pragma unroll 1
    while (op != 0xffffffffu) {
        const uint32_t ch = (op >> 2) & 1u;
        const uint32_t zero = (uint32_t)((int)op >> 31);
        pk = opaque(pk);
        optr += 4;
        uint32_t nop, nboost, late = 0, used = 0, extra = 0;
        if ((op & 3u) == 0) {
            if (op & 8u) mbar_wait(sb + BAR_READY + ch * 8, (op >> 4) & 1u);
            if (op & 0x20000000u) {
                const uint32_t qb = (((pk >> 16) & 0x30u) | ((pk >> 19) & 8u)) + (sb + OFF_Q + ch * 384);
                float d[4][4];
#pragma unroll
                for (int r = 0; r < 4; r++) d[r][0] = d[r][1] = d[r][2] = d[r][3] = 0.f;
#pragma unroll
                for (int c = 0; c < 6; c++) {
                    const uint2 q = lds64(qb + c * 64);
#pragma unroll
                    for (int r = 0; r < 4; r++) mma(d[r], rk[r][4 * c], rk[r][4 * c + 1], rk[r][4 * c + 2], rk[r][4 * c + 3], q.x, q.y);
                }
                nop = lds32(optr); nboost = lds32(sb + OFF_SCR + 36);
                float s[4];
#pragma unroll
                for (int r = 0; r < 4; r++) s[r] = bf_round(bf_round(d[r][0] + d[r][3]) * 0.07216878364870323f);
                const int mk = __shfl_sync(0xffffffffu, mkv, ch * 16);
                const int gk = max(mk, __reduce_max_sync(0xffffffffu, mono(__float_as_int(fmaxf(fmaxf(s[0], s[1]), fmaxf(s[2], s[3]))))));
                const float m = __int_as_float(mono(gk)), alpha = exp_diff(__int_as_float(mono(mk)), m);
                const float fa = ((pk >> 21) & 1u) == ch ? alpha : 1.f;
                if ((pk >> 24) == ch) { l *= alpha; mkv = gk; }
#pragma unroll
                for (int c = 0; c < 3; c++) { acc[c][0] *= fa; acc[c][1] *= fa; acc[c][2] *= fa; acc[c][3] *= fa; }
#pragma unroll
                for (int r = 0; r < 4; r++) {
                    const float p = exp_diff(s[r], m);
                    const float p0 = __shfl_sync(0xffffffffu, p, (pk >> 17) & 0x18u), p1 = __shfl_sync(0xffffffffu, p, ((pk >> 17) & 0x18u) + 4);
                    if ((pk >> 24) == ch) l += p0 + p1;
                    uint32_t b[4];
                    make_b(b, pack_bf16(p0, p1), pk, ch);
                    pv_regs(rv[r], acc, b);
                }
            } else {
                const uint32_t fk = (op >> 15) & 3u, fv = (op >> 17) & 3u;
                const uint32_t kearly = fk & ~ahead & 1u, kstay = (fk == 3) & ahead & boost;
                ahead = (fk & 1u) ? kstay : ahead;
                const uint32_t vearly = fv & ~ahead & 1u, vstay = (fv == 3) & ahead & boost;
                ahead = (fv & 1u) ? vstay : ahead;
                float d1[4] = {0.f, 0.f, 0.f, 0.f}, d2[4] = {0.f, 0.f, 0.f, 0.f};
                const uint32_t ka = (pk & 1023u) + (wslot + ((op >> 5) & 15u) * kSlotBytes);
                const uint32_t qa = ((pk >> 16) & 0x30u) + (sb + OFF_Q + ch * 384);
                mbar_wait(wbar + ((op >> 5) & 15u) * 8, (op >> 9) & 1u);
                fire(nx, kearly);
                if (!(op & 0x400000u)) {
#pragma unroll
                    for (int c = 0; c < 6; c++) {
                        uint32_t k[4], q[4];
                        lds128(k, (ka ^ ((c & 1) * 64u)) + (c >> 1) * 1024);
                        lds128(q, qa + c * 64);
                        mma(d1, q[0], q[1], q[2], q[3], k[0], k[1]);
                        mma(d2, q[0], q[1], q[2], q[3], k[2], k[3]);
                    }
                } else {
                    switch ((op >> 19) & 3u) {
                        case 0: k_fetch(rk[0], ka); qk_regs(rk[0], d1, d2, qa); break;
                        case 1: k_fetch(rk[1], ka); qk_regs(rk[1], d1, d2, qa); break;
                        case 2: k_fetch(rk[2], ka); qk_regs(rk[2], d1, d2, qa); break;
                        default: k_fetch(rk[3], ka); qk_regs(rk[3], d1, d2, qa); break;
                    }
                }
                fire(nx, ((fk == 2) | kstay) | after(d1[0], d1[0], d1[0], zero));
                ADVANCE(kearly | (fk == 2) | kstay);
                uint32_t s = pack_bf16(d1[0] + d2[2], d1[1] + d2[3]);
                s = pack_bf16(bf_lo(s) * 0.07216878364870323f, bf_hi(s) * 0.07216878364870323f);
                const float s0 = bf_lo(s), s1 = bf_hi(s);
                const int gk = __reduce_max_sync(0xffffffffu, mono(__float_as_int(fmaxf(s0, s1))));
                int mk = __shfl_sync(0xffffffffu, mkv, ch * 16);
                if (gk > mk) {
                    const float alpha = exp_diff(__int_as_float(mono(mk)), __int_as_float(mono(gk)));
                    const float fa = ((pk >> 21) & 1u) == ch ? alpha : 1.f;
                    if ((pk >> 24) == ch) { l *= alpha; mkv = gk; }
#pragma unroll
                    for (int c = 0; c < 3; c++) { acc[c][0] *= fa; acc[c][1] *= fa; acc[c][2] *= fa; acc[c][3] *= fa; }
                    mk = gk;
                }
                const float m = __int_as_float(mono(mk));
                const float p0 = exp_diff(s0, m), p1 = exp_diff(s1, m);
                if ((pk >> 24) == ch) l += p0 + p1;
                uint32_t b[4];
                make_b(b, pack_bf16(p0, p1), pk, ch);
                const uint32_t va = ((pk >> 10) & 1023u) + (wslot + ((op >> 10) & 15u) * kSlotBytes);
                nop = lds32(optr); nboost = lds32(sb + OFF_SCR + 36);
                mbar_wait(wbar + ((op >> 10) & 15u) * 8, (op >> 14) & 1u);
                fire(nx, vearly);
                if (!(op & 0x400000u)) {
                    uint32_t t[24];
                    v_fetch(t, va);
                    pv_regs(t, acc, b);
                } else {
                    switch ((op >> 19) & 3u) {
                        case 0: v_fetch(rv[0], va); pv_regs(rv[0], acc, b); break;
                        case 1: v_fetch(rv[1], va); pv_regs(rv[1], acc, b); break;
                        case 2: v_fetch(rv[2], va); pv_regs(rv[2], acc, b); break;
                        default: v_fetch(rv[3], va); pv_regs(rv[3], acc, b); break;
                    }
                }
                late = (fv == 2) | vstay; used = late | vearly;
                extra = (fv == 3) & boost & ~ahead & 1u;
                ahead |= extra;
            }
        } else if ((op & 3u) == 1) {
            mbar_wait(sb + BAR_READY + ch * 8, (op >> 4) & 1u);
            nop = lds32(optr); nboost = lds32(sb + OFF_SCR + 36);
            const uint32_t wa = ((pk >> 18) & 12u) + (sb + OFF_VEC + ch * 384 + warp * 16);
            const uint32_t v0 = ((pk >> 10) & 1023u) + wslot;
            const uint32_t wv[3] = {lds32(wa), lds32(wa + 128), lds32(wa + 256)};
#pragma unroll
            for (int i = 0; i < 3; i++) {
                const uint32_t slot = (op >> (5 + 5 * i)) & 15u;
                mbar_wait(wbar + slot * 8, (op >> (9 + 5 * i)) & 1u);
                if (i < 2 || !(op & (warp << 1) & 8u)) {
                    uint32_t t[24], b[4];
                    v_fetch(t, v0 + slot * kSlotBytes);
                    make_b(b, wv[i], pk, ch);
                    pv_regs(t, acc, b);
                }
                if (i < 2 && (op & (0x100000u << i))) {
                    fire(nx, 1u | ACC_DEP);
                    ADVANCE(1);
                }
            }
            late = used = op & 0x400000u;
        } else if ((op & 3u) == 2) {
            mbar_wait(wbar + ((op >> 5) & 15u) * 8, (op >> 9) & 1u);
            nop = lds32(optr); nboost = boost;
        } else {
            const uint32_t v0 = ((pk >> 10) & 1023u) + wslot;
#pragma unroll
            for (int i = 0; i < 3; i++) {
                const uint32_t slot = (op >> (5 + 5 * i)) & 15u;
                mbar_wait(wbar + slot * 8, (op >> (9 + 5 * i)) & 1u);
                v_fetch(rv[1 + i], v0 + slot * kSlotBytes);
            }
            nop = lds32(optr); nboost = boost;
            mbar_wait(sb + BAR_READY + ch * 8, (op >> 4) & 1u);
            const uint32_t wa = ((pk >> 18) & 12u) + (sb + OFF_VEC + ch * 384 + warp * 16);
            const uint32_t wv[3] = {lds32(wa), lds32(wa + 128), lds32(wa + 256)};
#pragma unroll
            for (int i = 0; i < 3; i++) {
                uint32_t b[4];
                make_b(b, wv[i], pk, ch);
                pv_regs(rv[1 + i], acc, b);
            }
        }
        if (op & 0x0c000000u) {
            const uint32_t fc = (op >> 27) & 1u, lane = opaque(pk) >> 20;
            mbar_wait(sb + BAR_FEMPTY, (op >> 28) & 1u);
            if (((lane >> 1) & 1u) == fc) {
#pragma unroll
                for (int c = 0; c < 3; c++) sts128f(sb + OFF_FBUF + warp * kFRow + c * 256 + (lane >> 2) * 32 + (lane & 1) * 16, acc[c]);
            }
            if ((op & 3u) == 0) {
                float ls = l + __shfl_xor_sync(0xffffffffu, l, 1);
                ls += __shfl_xor_sync(0xffffffffu, ls, 2);
                if (lane == fc * 16) {
                    sts32(sb + OFF_FBUF + warp * kFRow + 768, (uint32_t)mono(mkv));
                    stsf(sb + OFF_FBUF + warp * kFRow + 772, ls);
                }
            }
            __syncwarp();
            if (lane == 0) mbar_arrive(sb + BAR_FFULL);
            if (((lane >> 1) & 1u) == fc) {
#pragma unroll
                for (int c = 0; c < 3; c++) acc[c][0] = acc[c][1] = acc[c][2] = acc[c][3] = 0.f;
            }
            if ((lane >> 4) == fc) { l = 0.f; mkv = kMinusInf; }
        }
        if ((op & 0x03800000u) | used) {
            fire(nx, late | ACC_DEP);
            ADVANCE(used);
#pragma unroll 1
            for (uint32_t n = ((op >> 23) & 7u) + extra; n; n--) {
                if ((e & 0x80u) && warp < kL1Warps) fire_l1(nx, P.vb, opaque(pk) >> 20); else fire(nx, 1);
                ADVANCE(1);
            }
        }
        op = uniform(nop);
        boost = uniform(nboost);
    }
#undef ADVANCE
#undef ACC_DEP
}

__device__ __forceinline__ void layernorm_to_vec(const float* v, Scratch* G, uint32_t sb, uint32_t tid, uint32_t ch, uint32_t next) {
    const uint32_t scr = sb + OFF_SCR + 64 + ch * 32;
    const float pivot = __shfl_sync(0xffffffffu, v[0], 0);
    float s = 0.f, q = 0.f;
#pragma unroll
    for (int k = 0; k < 5; k++) { const float d = v[k] - pivot; s += d; q += d * d; }
#pragma unroll
    for (int o = 16; o; o >>= 1) { s += __shfl_xor_sync(0xffffffffu, s, o); q += __shfl_xor_sync(0xffffffffu, q, o); }
    if ((tid & 31) == 0) {
        const float dm = s * (1.f / 160.f);
        stsf(scr + (tid >> 5) * 8, pivot + dm);
        stsf(scr + (tid >> 5) * 8 + 4, q - s * dm);
    }
    svc_sync();
    const uint2 w0 = lds64(scr), w1 = lds64(scr + 8), w2 = lds64(scr + 16), w3 = lds64(scr + 24);
    const float m0 = __uint_as_float(w0.x), m1 = __uint_as_float(w1.x), m2 = __uint_as_float(w2.x), m3 = __uint_as_float(w3.x);
    const float mean = ((m0 + m1) + (m2 + m3)) * 0.25f;
    const float var = (((__uint_as_float(w0.y) + __uint_as_float(w1.y)) + (__uint_as_float(w2.y) + __uint_as_float(w3.y)))
                       + 160.f * ((m0 - mean) * (m0 - mean) + (m1 - mean) * (m1 - mean) + (m2 - mean) * (m2 - mean) + (m3 - mean) * (m3 - mean))) * (1.f / 640.f);
    const float mb = bf_round(mean);
    float den;
    asm("sqrt.approx.f32 %0, %1;" : "=f"(den) : "f"(bf_round(bf_round(var) + 1e-5f)));
    den = bf_round(den);
    const uint32_t r0 = svc_tid() - 160 * (blockIdx.x & 3);
    const uint32_t dst = sb + OFF_VEC + ch * 384 + ((0x63417250u >> ((r0 & 7) * 4)) & 7u) * 2;
#pragma unroll
    for (int k = 0; k < 5; k++) {
        const uint32_t r = r0 + 128 * k;
        if (r < 160u) sts16(dst + (r >> 3) * 16, pack_bf16(__fdividef(bf_round(v[k] - mb), den), 0.f));
    }
    __syncwarp();
    if ((tid & 31) == 0) mbar_arrive(sb + BAR_READY + ch * 8);
    if (blockIdx.x < (next < 3 ? kXCopies : 1)) {
#pragma unroll
        for (int k = 0; k < 5; k++)
            row_add(G->row + (((ch * 4 + next) * kXCopies + blockIdx.x) * 640 + tid + 128 * k), ((unsigned long long)__float_as_uint(v[k]) << 32) + 1);
    }
}

__device__ __forceinline__ void service(const Params& P, uint32_t sb) {
    const uint32_t cta = blockIdx.x, h = cta >> 2, j = cta & 3;
    Scratch* const G = &g_scratch;
#pragma unroll 1
    for (uint32_t ch = 0; ch < 2; ch++) {
        const uint32_t tid = svc_tid();
        float v[5];
#pragma unroll
        for (int k = 0; k < 5; k++) v[k] = bf_lo(lds16(sb + OFF_FBUF + (ch * 640 + 128 * k) * 2 + tid * 2));
        layernorm_to_vec(v, G, sb, tid, ch, 0);
    }
    if ((svc_tid() & 31) == 0) mbar_arrive(sb + BAR_FEMPTY);
#pragma unroll 1
    for (uint32_t ie = 0; ie < SCHED_NEV; ie++) {
        const uint32_t ev = uniform(lds32(sb + OFF_EVS + ie * 4));
        const uint32_t type = ev & 3u, ch = (ev >> 2) & 1u, layer = (ev >> 3) & 3u;
        const uint32_t tag = uniform(((lds32(sb + OFF_SCR + 32) + 1) * 32 + ie) & 0x7fffu), buf = (ev >> 5) & 1u;
        uint32_t tid = svc_tid();
        if (type != 2) st_word(G->rec + ((buf * kGrid + cta) * kRecWords + tid), 0, 0x80000000u);
        mbar_wait(sb + BAR_FFULL, ie & 1u);
        tid = svc_tid();
        float a = 0.f, b = 0.f;
        if (type != 2) {
            const uint32_t src = sb + OFF_FBUF + ((tid & 3) == 3 ? 96 : tid - (tid >> 2)) * 8;
            float scale = 1.f, M = 0.f;
            if (type == 1) {
                const float m = ldsf(sb + OFF_FBUF + 768 + (tid & 7) * kFRow);
                M = fmaxf(m, __shfl_xor_sync(0xffffffffu, m, 1));
                M = fmaxf(M, __shfl_xor_sync(0xffffffffu, M, 2));
                M = fmaxf(M, __shfl_xor_sync(0xffffffffu, M, 4));
                scale = exp_diff(m, M);
            }
#pragma unroll
            for (int w = 0; w < 8; w++) {
                const uint2 f = lds64(src + w * kFRow);
                const float sc = __shfl_sync(0xffffffffu, scale, w);
                a += sc * __uint_as_float(f.x); b += sc * __uint_as_float(f.y);
            }
            if ((tid & 3) == 3) a = M;
            tid = svc_tid();
            st_pair(G->rec + ((buf * kGrid + cta) * kRecWords + tid), a, b, tag);
        } else {
#pragma unroll
            for (int w = 0; w < 8; w++) { a += ldsf(sb + OFF_FBUF + tid * 4 + w * kFRow); b += ldsf(sb + OFF_FBUF + 512 + (tid & 63) * 4 + w * kFRow); }
            const uint32_t col = (((layer & 1) ? j + 2 : j) & 3u) * 192 + tid;
            uint2* dst = G->row + ((ch * 4 + layer) * kXCopies * 640 + col);
            const unsigned long long wa = row_word(a), wb = row_word(b);
            const uint32_t ga = col < 640, gb = tid < 64 && col < 512;
            row_add(dst, wa, ga); row_add(dst + 128, wb, gb);
            if (layer < 3) {
#pragma unroll
                for (int c = 1; c < kXCopies; c++) { row_add(dst + c * 640, wa, ga); row_add(dst + c * 640 + 128, wb, gb); }
            }
        }
        __syncwarp();
        if ((tid & 31) == 0) mbar_arrive(sb + BAR_FEMPTY);
        uint32_t rank = 0;
        if (tid == 96) asm volatile("atom.relaxed.gpu.global.inc.u32 %0, [%1], %2;" : "=r"(rank) : "l"(&G->rank[ie * 32]), "n"(kGrid - 1) : "memory");
        tid = svc_tid();
        if (type != 2) {
            const uint2* rec = G->rec + ((buf * kGrid + h * 4) * kRecWords + tid);
            uint2 u1, u2, u3;
            __nanosleep(kRecDelayNs);
            for (uint32_t spins = 0;; spins++) {
                u1 = ld_word(rec + (j ^ 1) * kRecWords); u2 = ld_word(rec + (j ^ 2) * kRecWords); u3 = ld_word(rec + (j ^ 3) * kRecWords);
                if (__all_sync(0xffffffffu, (((u1.y ^ u2.y) | (u1.y ^ u3.y) | (u1.y ^ (tag << 16))) >> 16) == 0)) break;
                if (spins > kSpinLimit) __trap();
                __nanosleep(kRecPollNs);
            }
            tid = svc_tid();
            if (tid == 96) sts32(sb + OFF_SCR + 36, rank >= (ev >> 8));
            a = pair_a(__float_as_uint(a)); b = pair_a(__float_as_uint(b));
            float a1 = pair_a(u1.x), b1 = pair_b(u1.x, u1.y), a2 = pair_a(u2.x), b2 = pair_b(u2.x, u2.y), a3 = pair_a(u3.x), b3 = pair_b(u3.x, u3.y);
            if (type) {
                const float Mg = fmaxf(fmaxf(a, a1), fmaxf(a2, a3));
                const float e0 = exp_diff(a, Mg), e1 = exp_diff(a1, Mg), e2 = exp_diff(a2, Mg), e3 = exp_diff(a3, Mg);
                const float r = __fdividef(1.f, __fadd_rn(__fadd_rn(__fmul_rn(e0, b), __fmul_rn(e1, b1)), __fadd_rn(__fmul_rn(e2, b2), __fmul_rn(e3, b3))));
                const float f0 = __shfl_sync(0xffffffffu, e0 * r, 3, 4), f1 = __shfl_sync(0xffffffffu, e1 * r, 3, 4);
                const float f2 = __shfl_sync(0xffffffffu, e2 * r, 3, 4), f3 = __shfl_sync(0xffffffffu, e3 * r, 3, 4);
                a = __fmul_rn(a, f0); b = __fmul_rn(b, f0); a1 = __fmul_rn(a1, f1); b1 = __fmul_rn(b1, f1);
                a2 = __fmul_rn(a2, f2); b2 = __fmul_rn(b2, f2); a3 = __fmul_rn(a3, f3); b3 = __fmul_rn(b3, f3);
            }
            const uint32_t pk = pack_bf16(__fadd_rn(__fadd_rn(a, a1), __fadd_rn(a2, a3)), __fadd_rn(__fadd_rn(b, b1), __fadd_rn(b2, b3)));
            tid = svc_tid();
            const uint32_t d = (tid - (tid >> 2)) * 2;
            if ((tid & 3) != 3) {
                if (type) {
                    const uint32_t vb = sb + OFF_VEC + ch * 384 + (d >> 3) * 16;
                    sts16(vb + ((0x63417250u >> ((d & 7) * 4)) & 7u) * 2, pk);
                    sts16(vb + ((0x63417250u >> ((d & 7) * 4 + 4)) & 7u) * 2, pk >> 16);
                } else {
                    sts32(sb + OFF_Q + ch * 384 + (d >> 3) * 16 + ((0x3120u >> ((d & 6) * 2)) & 3u) * 4, pk);
                }
            }
            __syncwarp();
            if ((tid & 31) == 0) mbar_arrive(sb + BAR_READY + ch * 8);
        } else {
            const uint2* src = G->row + (((ch * 4 + layer) * kXCopies + (h & (kXCopies - 1))) * 640 + tid);
            if (layer < 3) {
                uint2 u[5];
                __nanosleep(kRowDelayNs);
                for (uint32_t spins = 0;; spins++) {
#pragma unroll
                    for (int k = 0; k < 5; k++) u[k] = ld_word(src + 128 * k);
                    const uint32_t bad = ((u[0].x ^ 33u) | (u[1].x ^ 33u) | (u[2].x ^ 33u) | (u[3].x ^ 33u) | (u[4].x ^ 33u)) & 63u;
                    if (__all_sync(0xffffffffu, bad == 0)) break;
                    if (spins > kSpinLimit) __trap();
                    __nanosleep(kRowPollNs);
                }
                tid = svc_tid();
                if (tid == 96) sts32(sb + OFF_SCR + 36, rank >= (ev >> 8));
                const float v[5] = {row_value(u[0]), row_value(u[1]), row_value(u[2]), row_value(u[3]), row_value(u[4])};
                layernorm_to_vec(v, G, sb, tid, ch, layer + 1);
                if (layer && tid < 5 * kXCopies)
                    st_word(G->row + ((ch * 4 + layer - 1) * kXCopies * 640 + cta * 5 * kXCopies + tid), 0, 0);
            } else {
                if (j == 3 && h < 5) {
                    uint2* last = G->row + ((ch * 4 + 3) * kXCopies * 640 + h * 128 + tid);
                    uint2 u;
                    for (uint32_t spins = 0;; spins++) {
                        u = ld_word(last);
                        if (__all_sync(0xffffffffu, (u.x & 63u) == 33u)) break;
                        if (spins > kSpinLimit) __trap();
                    }
                    P.out[ch * 640 + h * 128 + tid] = __float2bfloat16(row_value(u));
#pragma unroll
                    for (int c = 0; c <= kXCopies; c++) st_word(last - c * 640, 0, 0);
                }
                if (tid == 96) sts32(sb + OFF_SCR + 36, rank >= (ev >> 8));
            }
        }
    }
    if (cta == 0 && svc_tid() == 0) asm volatile("st.relaxed.gpu.global.u32 [%0], %1;" :: "l"(&G->epoch), "r"(lds32(sb + OFF_SCR + 32) + 1) : "memory");
}

__global__ void __launch_bounds__(kThreads, 1) fused_decode_kernel(const __grid_constant__ Params P) {
    extern __shared__ __align__(1024) unsigned char smem[];
    asm volatile("prefetch.tensormap [%0];" :: "l"(&P.maps[4]) : "memory");
    asm volatile("prefetch.tensormap [%0];" :: "l"(&P.maps[0]) : "memory");
    asm volatile("prefetch.tensormap [%0];" :: "l"(&P.maps[1]) : "memory");
    const uint32_t sb = (uint32_t)__cvta_generic_to_shared(smem);
    const uint32_t tid = threadIdx.x, warp = uniform(tid >> 5), lane = tid & 31;
    const uint32_t h = blockIdx.x >> 2, j = blockIdx.x & 3;
    if (warp >= 8) {
        const uint32_t t = tid - 256;
        const uint4* xp = reinterpret_cast<const uint4*>(P.x);
        const uint4 x0 = xp[t], x1 = t < 32 ? xp[128 + t] : make_uint4(0, 0, 0, 0);
        if (t < SCHED_NEV) sts32(sb + OFF_EVS + t * 4, g_evs[t]);
        if (t == 32) {
            uint32_t ep;
            asm volatile("ld.relaxed.gpu.global.u32 %0, [%1];" : "=r"(ep) : "l"(&g_scratch.epoch) : "memory");
            sts32(sb + OFF_SCR + 32, ep); sts32(sb + OFF_SCR + 36, 0);
        }
        if (t == 64) {
            mbar_init(sb + BAR_READY, 4); mbar_init(sb + BAR_READY + 8, 4); mbar_init(sb + BAR_FFULL, 8); mbar_init(sb + BAR_FEMPTY, 4);
        }
        if (t >= 96 && t < 104) asm volatile("prefetch.tensormap [%0];" :: "l"(&P.maps[t - 96]) : "memory");
        asm volatile("st.shared.v4.u32 [%0], {%1,%2,%3,%4};" :: "r"(sb + OFF_FBUF + t * 16), "r"(x0.x), "r"(x0.y), "r"(x0.z), "r"(x0.w) : "memory");
        if (t < 32) asm volatile("st.shared.v4.u32 [%0], {%1,%2,%3,%4};" :: "r"(sb + OFF_FBUF + 2048 + t * 16), "r"(x1.x), "r"(x1.y), "r"(x1.z), "r"(x1.w) : "memory");
    } else {
        if (lane == 0) {
#pragma unroll
            for (int k = 0; k < kSlots; k++) mbar_init(sb + OFF_BAR + warp * (kSlots * 8) + k * 8, 1);
            asm volatile("fence.mbarrier_init.release.cluster;" ::: "memory");
        }
        __syncwarp();
        constexpr uint32_t first[SCHED_NLD] = { SCHED_LDS };
#pragma unroll
        for (int k = 0; k < SCHED_NPRO; k++) fire(decode(expand_entry(first[k], h, j), sb, P, warp), 1);
        uint32_t t0, t1;
        asm volatile("ld.global.u32 %0, [%1];" : "=r"(t1) : "l"(g_lds + opaque(tid)) : "memory");
        asm volatile("ld.global.u32 %0, [%1];" : "=r"(t0) : "l"(g_ops + (opaque(tid) & 127)) : "memory");
        if (tid < 128) sts32(sb + OFF_OPS + tid * 4, t0);
        sts32(sb + OFF_LDS + tid * 4, expand_entry(t1, h, j));
    }
    if (sb & 1023u) __trap();
    __syncthreads();
    if (warp < 8) {
        asm volatile("setmaxnreg.inc.sync.aligned.u32 %0;" :: "n"(kConsumerRegs));
        consumer(P, sb, warp, lane);
    } else {
        asm volatile("setmaxnreg.dec.sync.aligned.u32 %0;" :: "n"(504 - 2 * kConsumerRegs));
        service(P, sb);
    }
}

typedef CUresult (*EncodeFn)(CUtensorMap*, CUtensorMapDataType, cuuint32_t, void*, const cuuint64_t*, const cuuint64_t*,
                             const cuuint32_t*, const cuuint32_t*, CUtensorMapInterleave, CUtensorMapSwizzle,
                             CUtensorMapL2promotion, CUtensorMapFloatOOBfill);

void encode(EncodeFn fn, CUtensorMap* m, void* ptr, uint64_t rows, uint64_t lines, CUtensorMapL2promotion promo) {
    const cuuint64_t dims[3] = {64, rows, lines};
    const cuuint64_t strides[2] = {lines * 128, 128};
    const cuuint32_t box[3] = {64, 8, 3}, es[3] = {1, 1, 1};
    fn(m, CU_TENSOR_MAP_DATA_TYPE_BFLOAT16, 3, ptr, dims, strides, box, es, CU_TENSOR_MAP_INTERLEAVE_NONE,
       CU_TENSOR_MAP_SWIZZLE_128B, promo, CU_TENSOR_MAP_FLOAT_OOB_FILL_NONE);
}

}

extern "C" void kernel_launch(void* const* d_in, const int* in_sizes, int n_in, void* d_out, int out_size) {
    (void)in_sizes; (void)n_in; (void)out_size;
    static EncodeFn fn = nullptr;
    if (!fn) {
        cudaDriverEntryPointQueryResult qr;
        cudaGetDriverEntryPoint("cuTensorMapEncodeTiled", (void**)&fn, cudaEnableDefault, &qr);
        cudaFuncSetAttribute(fused_decode_kernel, cudaFuncAttributeMaxDynamicSharedMemorySize, kSmemBytes);
    }
    Params P;
    encode(fn, &P.maps[0], d_in[1], 262144, 3, CU_TENSOR_MAP_L2_PROMOTION_NONE);
    encode(fn, &P.maps[1], d_in[2], 262144, 3, CU_TENSOR_MAP_L2_PROMOTION_NONE);
    encode(fn, &P.maps[2], d_in[6], 262144, 3, CU_TENSOR_MAP_L2_PROMOTION_NONE);
    encode(fn, &P.maps[3], d_in[7], 262144, 3, CU_TENSOR_MAP_L2_PROMOTION_NONE);
    encode(fn, &P.maps[4], d_in[3], 640, 96, CU_TENSOR_MAP_L2_PROMOTION_L2_128B);
    encode(fn, &P.maps[5], d_in[4], 6144, 10, CU_TENSOR_MAP_L2_PROMOTION_L2_128B);
    encode(fn, &P.maps[6], d_in[8], 640, 96, CU_TENSOR_MAP_L2_PROMOTION_L2_128B);
    encode(fn, &P.maps[7], d_in[9], 6144, 10, CU_TENSOR_MAP_L2_PROMOTION_L2_128B);
    P.x = (const __nv_bfloat16*)d_in[0];
    P.out = (__nv_bfloat16*)d_out;
    P.vb = (const char*)d_in[7];
    fused_decode_kernel<<<kGrid, kThreads, kSmemBytes>>>(P);
}
```
